```python
import torch

def _softmax(x, axis=-1):
    return torch.softmax(x, dim=axis)
def _gelu(x):
    return torch.nn.functional.gelu(x, approximate="tanh")
def _silu(x):
    return torch.nn.functional.silu(x)
def _sigmoid(x):
    return torch.sigmoid(x)
def _layernorm(x, axis=-1, eps=1e-5):
    m = x.mean(dim=axis, keepdim=True)
    v = x.var(dim=axis, keepdim=True, unbiased=False)
    return (x - m) / torch.sqrt(v + eps)
def _scatter_add(tgt, idx, src, axis=0):
    return tgt.clone().index_add_(axis, idx, src)
def _segment_sum(src, seg, n):
    out = torch.zeros((n,) + src.shape[1:], dtype=src.dtype)
    return out.index_add_(0, seg, src)
def _pad(x, pw):
    flat = tuple(v for pair in reversed(pw) for v in pair)
    return torch.nn.functional.pad(x, flat)

kernel_name = 'sequential_preLN__grouped_kv_mqa__dense_activation_gelu__prompt'

def setup_inputs():

    _w = (lambda a: (lambda t: t.to(torch.bfloat16) if t.is_floating_point() else t)(torch.as_tensor(a)))
    def _A_setup():
        B, S, D, H = 1, 2048, 448, 16
        Dh = D // H
        return {
            "x": _w((lambda *s: torch.randn(*s, dtype=torch.bfloat16) * 0.05)(B, S, D)),
            "wq": _w((lambda *s: torch.randn(*s, dtype=torch.bfloat16) * 0.05)(D, H * Dh)),
            "wk": _w((lambda *s: torch.randn(*s, dtype=torch.bfloat16) * 0.05)(D, Dh)),
            "wv": _w((lambda *s: torch.randn(*s, dtype=torch.bfloat16) * 0.05)(D, Dh)),
            "wo": _w((lambda *s: torch.randn(*s, dtype=torch.bfloat16) * 0.05)(H * Dh, D)),
        }
    _A_in = _A_setup()

    def _B_setup():
        B, S, D, F = 1, 2048, 448, 1792
        return {
            "x": _w((lambda *s: torch.randn(*s, dtype=torch.bfloat16) * 0.05)(B, S, D)),
            "w1": _w((lambda *s: torch.randn(*s, dtype=torch.bfloat16) * 0.8)(D, F) * (D ** -0.5)),
            "b1": _w((lambda *s: torch.randn(*s, dtype=torch.bfloat16) * 12.8)(F) * 0.01),
            "w2": _w((lambda *s: torch.randn(*s, dtype=torch.bfloat16) * 0.4)(F, D) * (F ** -0.5)),
            "b2": _w((lambda *s: torch.randn(*s, dtype=torch.bfloat16) * 6.4)(D) * 0.01),
        }
    _B_in = _B_setup()

    return {
        "A_x": _A_in["x"],
        "A_wq": _A_in["wq"],
        "A_wk": _A_in["wk"],
        "A_wv": _A_in["wv"],
        "A_wo": _A_in["wo"],
        "B_x": _B_in["x"],
        "B_w1": _B_in["w1"],
        "B_b1": _B_in["b1"],
        "B_w2": _B_in["w2"],
        "B_b2": _B_in["b2"],
    }

def reference(A_x, A_wq, A_wk, A_wv, A_wo, B_x, B_w1, B_b1, B_w2, B_b2):
    def _A_ref(x, wq, wk, wv, wo):
        B, S, D = x.shape
        H = 16
        Dh = D // H
        q = (lambda x, *d: x.permute(*d))((x @ wq).reshape(B, S, H, Dh), 0, 2, 1, 3)
        k = x @ wk
        v = x @ wv
        scores = torch.einsum("bhqd,bkd->bhqk", q, k) * (Dh ** -0.5)
        p = _softmax(scores, axis=-1)
        o = torch.einsum("bhqk,bkd->bhqd", p, v)
        return (lambda x, *d: x.permute(*d))(o, 0, 2, 1, 3).reshape(B, S, H * Dh) @ wo

    def _B_ref(x, w1, b1, w2, b2):
        h = torch.einsum("bsd,df->bsf", x, w1) + b1
        h = _gelu(h)
        return torch.einsum("bsf,fd->bsd", h, w2) + b2

    x = A_x
    h = x + _A_ref(_layernorm(x, axis=-1), A_wq, A_wk, A_wv, A_wo)
    h2 = h + _B_ref(_layernorm(h, axis=-1), B_w1, B_b1, B_w2, B_b2)
    return h2
```

```cpp
#include <cuda_runtime.h>
#include <cuda_bf16.h>
#include <cuda.h>
#include <stdint.h>

#define EA_EARLY 0
#define CLUSTER 0
#define PAIR_I 1
#define X_LATE 1
#define QNOWAIT 1
#define FENCE_FIRST 1
#define EC_AT 1
#define IDLE 2
#define HINT2 ", 20000"
#define RDWAIT 1
#define POLL_ALL 0
#define POLL_LATE 1
#define POLL_SLEEP 0
#define REDREL 1
#define KVWG 0
#define OSEQ 1
#define XW0 1
#define WQ_AT 0
#define WQ_EARLY 4
#define WQ_MID 4

namespace {

constexpr int SEQ = 2048, DM = 448, FF = 1792;
constexpr int NCTA = 128;
constexpr int NTHREADS = 640;

constexpr uint32_t SMEM_BASE = 1024;
constexpr uint32_t OFF_A = 0;
constexpr uint32_t OFF_B = 57344;
constexpr uint32_t OFF_C = 114688;
constexpr uint32_t OFF_X = 229376;
constexpr uint32_t OFF_Q = 98304;
constexpr uint32_t BAR_EP = OFF_X;
constexpr uint32_t BAR_WQ = BAR_EP + 8;
constexpr uint32_t BAR_KVF = BAR_WQ + 4 * 8;
constexpr uint32_t BAR_WO = BAR_KVF + 6 * 8;
constexpr uint32_t BAR_KM = BAR_WO + 8;
constexpr uint32_t BAR_RF = BAR_KM + 8;
constexpr uint32_t BAR_OI = BAR_RF + 50 * 8;
constexpr uint32_t BAR_KVE = OFF_X + 64 * 8;
constexpr uint32_t BAR_H1 = BAR_KVE + 6 * 8;
constexpr uint32_t BAR_F1 = BAR_H1 + 4 * 8;
constexpr uint32_t BAR_WH = BAR_F1 + 8;
constexpr uint32_t BAR_RSTD = OFF_X + 76 * 8;
constexpr uint32_t BAR_END = BAR_RSTD + 8;
constexpr uint32_t BAR_FREE = OFF_X + 80 * 8;
constexpr uint32_t BAR_X = OFF_X + 132 * 8;
constexpr uint32_t OFF_RSTD = OFF_X + 136 * 8;
constexpr uint32_t OFF_QMAX = OFF_RSTD + 256;
constexpr uint32_t OFF_KMAX = OFF_QMAX + 64;
constexpr uint32_t OFF_EPOCH = OFF_KMAX + 512;
constexpr uint32_t OFF_SLOW = OFF_EPOCH + 16;
constexpr uint32_t OFF_B1 = OFF_SLOW + 16;
constexpr uint32_t SMEM_BYTES = OFF_X + 3072;
static_assert(OFF_B1 + 896 <= SMEM_BYTES && OFF_B1 % 16 == 0, "smem map");

constexpr uint32_t SENTINEL = 0xFFFFFFFFu;
#define PMASK 0xF8F8
constexpr int POLY_MASK = PMASK;
constexpr float SCORE_BOUND = 60.0f;

}

struct Scratch {
  unsigned epoch[32];
  unsigned kvflag[16 * 32];
  unsigned rstflag[32 * 32];
  unsigned iniflag[32 * 32];
  unsigned short kmax[256];
  uint4 kv[16 * 1024];
  uint4 h[32 * 4096];
  uint4 o[32 * 4096];
};
__device__ __align__(128) Scratch g_s;
#define g_kvflag g_s.kvflag
#define g_rstflag g_s.rstflag
#define g_iniflag g_s.iniflag
#define g_kmax g_s.kmax
#define g_h g_s.h
#define g_o g_s.o
#define TS(slot) do {} while (0)
#define TSP(slot) do {} while (0)
#define TSG(slot) do {} while (0)
#define TSD(slot, dep) do {} while (0)
#define PROF_PARAM
#define PROF_ARG

#define TSA(slot) do {} while (0)
#define TSF(slot) do {} while (0)
#define TS2(n, k) do {} while (0)

namespace {

__device__ __forceinline__ uint32_t smem_base() { return SMEM_BASE + (CLUSTER ? (blockIdx.x & 1) << 24 : 0u); }
__device__ __forceinline__ int cta_i() { return PAIR_I == 2 ? (blockIdx.x & 15) + (blockIdx.x >> 6) * 16 : PAIR_I == 3 ? (blockIdx.x & 3) + (blockIdx.x >> 4) * 4 : PAIR_I ? blockIdx.x >> 2 : (blockIdx.x >> 3) * 2 + (blockIdx.x & 1); }
__device__ __forceinline__ int cta_j() { return PAIR_I == 2 ? (blockIdx.x >> 4) & 3 : PAIR_I == 3 ? (blockIdx.x >> 2) & 3 : PAIR_I ? blockIdx.x & 3 : (blockIdx.x >> 1) & 3; }
__device__ __forceinline__ void mbar_init(uint32_t b, uint32_t count) {
  asm volatile("mbarrier.init.shared::cta.b64 [%0], %1;" ::"r"(b), "r"(count) : "memory");
}
__device__ __forceinline__ void mbar_expect(uint32_t b, uint32_t bytes) {
  asm volatile("mbarrier.arrive.expect_tx.shared::cta.b64 _, [%0], %1;" ::"r"(b), "r"(bytes) : "memory");
}
__device__ __forceinline__ void mbar_arrive(uint32_t b) {
  asm volatile("mbarrier.arrive.shared::cta.b64 _, [%0];" ::"r"(b) : "memory");
}
__device__ __forceinline__ uint32_t mbar_try(uint32_t b, uint32_t parity) {
  uint32_t ok;
  asm volatile("{.reg .pred p; mbarrier.try_wait.parity.shared::cta.b64 p, [%1], %2; selp.u32 %0, 1, 0, p;}"
               : "=r"(ok) : "r"(b), "r"(parity) : "memory");
  return ok;
}
#define SPIN_LIMIT(it, code) \
  asm volatile("{.reg .pred p; setp.gt.s32 p, %0, 4194304; @p st.volatile.global.u32 [%1], %0;}" ::"r"(it), "l"(0ull) : "memory");
__device__ __forceinline__ void mbar_wait(uint32_t b, uint32_t parity) {
  asm volatile(
      "{.reg .pred p; .reg .u32 c;\n"
      "mov.u32 c, 0;\n"
      "W_%=: mbarrier.try_wait.parity.shared::cta.b64 p, [%0], %1;\n"
      "vote.sync.all.pred p, p, 0xffffffff;\n"
      "@p bra.uni D_%=;\n"
      "add.u32 c, c, 1;\n"
      "setp.gt.u32 p, c, 4194304;\n"
      "@p trap;\n"
      "bra.uni W_%=;\n"
      "D_%=: }" ::"r"(b), "r"(parity) : "memory");
}
__device__ __forceinline__ void mbar_finish(uint32_t ok, uint32_t b, uint32_t parity) {
  asm volatile(
      "{.reg .pred p; .reg .u32 c;\n"
      "setp.ne.u32 p, %2, 0;\n"
      "@p bra.uni D_%=;\n"
      "mov.u32 c, 0;\n"
      "W_%=: mbarrier.try_wait.parity.shared::cta.b64 p, [%0], %1;\n"
      "@p bra.uni D_%=;\n"
      "add.u32 c, c, 1;\n"
      "setp.gt.u32 p, c, 4194304;\n"
      "@p trap;\n"
      "bra.uni W_%=;\n"
      "D_%=: }" ::"r"(b), "r"(parity), "r"(ok) : "memory");
}
__device__ __forceinline__ void mbar_finish2(uint32_t ok, uint32_t b0, uint32_t b1) {
  asm volatile(
      "{.reg .pred p, q; .reg .u32 c;\n"
      "setp.ne.u32 p, %2, 0;\n"
      "@p bra.uni D_%=;\n"
      "mov.u32 c, 0;\n"
      "W_%=: mbarrier.try_wait.parity.shared::cta.b64 p, [%0], 0" HINT2 ";\n"
      "mbarrier.try_wait.parity.shared::cta.b64 q, [%1], 0" HINT2 ";\n"
      "and.pred p, p, q;\n"
      "@p bra.uni D_%=;\n"
      "add.u32 c, c, 1;\n"
      "setp.gt.u32 p, c, 4194304;\n"
      "@p trap;\n"
      "bra.uni W_%=;\n"
      "D_%=: }" ::"r"(b0), "r"(b1), "r"(ok) : "memory");
}
__device__ __forceinline__ void mbar_wait_idle(uint32_t b, uint32_t parity) {
  asm volatile(
      "{.reg .pred p; .reg .u32 c;\n"
      "mov.u32 c, 0;\n"
      "W_%=: mbarrier.try_wait.parity.shared::cta.b64 p, [%0], %1, 20000;\n"
      "vote.sync.all.pred p, p, 0xffffffff;\n"
      "@p bra.uni D_%=;\n"
      "add.u32 c, c, 1;\n"
      "setp.gt.u32 p, c, 100000;\n"
      "@p trap;\n"
      "bra.uni W_%=;\n"
      "D_%=: }" ::"r"(b), "r"(parity) : "memory");
}
__device__ __forceinline__ void mbar_wait_lane(uint32_t b) {
  asm volatile(
      "{.reg .pred p; .reg .u32 c;\n"
      "mov.u32 c, 0;\n"
      "W_%=: mbarrier.try_wait.parity.shared::cta.b64 p, [%0], 0, 20000;\n"
      "@p bra.uni D_%=;\n"
      "add.u32 c, c, 1;\n"
      "setp.gt.u32 p, c, 100000;\n"
      "@p trap;\n"
      "bra.uni W_%=;\n"
      "D_%=: }" ::"r"(b) : "memory");
}
__device__ __forceinline__ bool elect() {
  uint32_t e;
  asm volatile("{.reg .pred p; elect.sync _|p, 0xffffffff; selp.u32 %0, 1, 0, p;}" : "=r"(e));
  return e;
}
__device__ __forceinline__ void bar_sync(int id, int n) { asm volatile("bar.sync %0, %1;" ::"r"(id), "r"(n) : "memory"); }
__device__ __forceinline__ void bar_arrive(int id, int n) { asm volatile("bar.arrive %0, %1;" ::"r"(id), "r"(n) : "memory"); }
__device__ __forceinline__ void fence_async_smem() { asm volatile("fence.proxy.async.shared::cta;" ::: "memory"); }
__device__ __forceinline__ void fence_async_global() { asm volatile("fence.proxy.async.global;" ::: "memory"); }
__device__ __forceinline__ void wg_fence() { asm volatile("wgmma.fence.sync.aligned;" ::: "memory"); }
__device__ __forceinline__ void wg_commit() { asm volatile("wgmma.commit_group.sync.aligned;" ::: "memory"); }
template <int N>
__device__ __forceinline__ void wg_wait() { asm volatile("wgmma.wait_group.sync.aligned %0;" ::"n"(N) : "memory"); }
template <int N>
__device__ __forceinline__ void pin(float* x) {
#pragma unroll
  for (int i = 0; i < N; i++) asm volatile("" : "+f"(x[i])::"memory");
}
template <int N>
__device__ __forceinline__ void pin(uint32_t* x) {
#pragma unroll
  for (int i = 0; i < N; i++) asm volatile("" : "+r"(x[i])::"memory");
}
__device__ __forceinline__ uint64_t mkdesc(uint32_t addr, uint32_t lbo, uint32_t sbo, uint32_t swz) {
  return (uint64_t)((addr & 0x3FFFF) >> 4) | ((uint64_t)(lbo >> 4) << 16) | ((uint64_t)(sbo >> 4) << 32) | ((uint64_t)swz << 62);
}
__device__ __forceinline__ void tma2d(uint32_t dst, const CUtensorMap* tm, int c0, int c1, uint32_t bar) {
  asm volatile("cp.async.bulk.tensor.2d.shared::cluster.global.mbarrier::complete_tx::bytes [%0], [%1, {%3,%4}], [%2];"
               ::"r"(dst), "l"(tm), "r"(bar), "r"(c0), "r"(c1) : "memory");
}
__device__ __forceinline__ void tma4d(uint32_t dst, const CUtensorMap* tm, int c0, int c1, int c2, int c3, uint32_t bar) {
  asm volatile("cp.async.bulk.tensor.4d.shared::cluster.global.mbarrier::complete_tx::bytes [%0], [%1, {%3,%4,%5,%6}], [%2];"
               ::"r"(dst), "l"(tm), "r"(bar), "r"(c0), "r"(c1), "r"(c2), "r"(c3) : "memory");
}
__device__ __forceinline__ void bulk_load(uint32_t dst, const void* src, uint32_t bytes, uint32_t bar) {
  asm volatile("cp.async.bulk.shared::cluster.global.mbarrier::complete_tx::bytes [%0], [%1], %2, [%3];"
               ::"r"(dst), "l"(src), "r"(bytes), "r"(bar) : "memory");
}
__device__ __forceinline__ void l2_prefetch(const void* src, uint32_t bytes) {
  asm volatile("cp.async.bulk.prefetch.L2.global [%0], %1;" ::"l"(src), "r"(bytes) : "memory");
}
__device__ __forceinline__ unsigned ld_acquire(const unsigned* p) {
  unsigned v;
  asm volatile("ld.acquire.gpu.global.u32 %0, [%1];" : "=r"(v) : "l"(p) : "memory");
  return v;
}
__device__ __forceinline__ void publish(unsigned* flag) {
  asm volatile("red.release.gpu.global.add.u32 [%0], 1;" ::"l"(flag) : "memory");
}
__device__ __forceinline__ void wait_flag(const unsigned* p, unsigned target) {
  for (int it = 0; (int)(ld_acquire(p) - target) < 0; it++) { SPIN_LIMIT(it, 1000) }
}
__device__ __forceinline__ uint4 ld_relaxed4(const uint4* p) {
  uint4 v;
  asm volatile("ld.relaxed.gpu.global.v4.u32 {%0,%1,%2,%3}, [%4];" : "=r"(v.x), "=r"(v.y), "=r"(v.z), "=r"(v.w) : "l"(p) : "memory");
  return v;
}
__device__ __forceinline__ void ld_relaxed4_if(uint4& v, const uint4* p, bool pred) {
  asm volatile("{.reg .pred q; setp.ne.u32 q, %5, 0; @q ld.relaxed.gpu.global.v4.u32 {%0,%1,%2,%3}, [%4];}"
               : "+r"(v.x), "+r"(v.y), "+r"(v.z), "+r"(v.w) : "l"(p), "r"((uint32_t)pred) : "memory");
}
__device__ __forceinline__ void st_relaxed4(uint4* p, const uint4& v) {
  asm volatile("st.relaxed.gpu.global.v4.u32 [%0], {%1,%2,%3,%4};" ::"l"(p), "r"(v.x), "r"(v.y), "r"(v.z), "r"(v.w) : "memory");
}
template <int N>
__device__ __forceinline__ void poll_chunks(uint4* v, const uint4* const* p) {
  for (int it = 0;; it++) {
    uint32_t m[N], all = 0;
#pragma unroll
    for (int t = 0; t < N; t++) {
      m[t] = max(__vimax3_u32(v[t].x, v[t].y, v[t].z), v[t].w);
      all = max(all, m[t]);
    }
    if (!__any_sync(0xffffffffu, all == SENTINEL)) break;
#pragma unroll
    for (int t = 0; t < N; t++) ld_relaxed4_if(v[t], p[t], m[t] == SENTINEL);
    SPIN_LIMIT(it, 2100 + N)
  }
}
__device__ __forceinline__ uint4 lds128(uint32_t a) {
  uint4 v;
  asm volatile("ld.shared.v4.u32 {%0,%1,%2,%3}, [%4];" : "=r"(v.x), "=r"(v.y), "=r"(v.z), "=r"(v.w) : "r"(a) : "memory");
  return v;
}
__device__ __forceinline__ uint32_t lds32(uint32_t a) {
  uint32_t v;
  asm volatile("ld.shared.u32 %0, [%1];" : "=r"(v) : "r"(a) : "memory");
  return v;
}
__device__ __forceinline__ void sts32(uint32_t a, uint32_t v) { asm volatile("st.shared.u32 [%0], %1;" ::"r"(a), "r"(v) : "memory"); }
__device__ __forceinline__ uint32_t bf2add(uint32_t a, uint32_t b) {
  uint32_t d;
  asm("fma.rn.bf16x2 %0, %1, %2, %3;" : "=r"(d) : "r"(a), "r"(0x3F803F80u), "r"(b));
  return d;
}
__device__ __forceinline__ uint32_t bf2mul(uint32_t a, uint32_t b) {
  uint32_t d;
  asm("mul.rn.bf16x2 %0, %1, %2;" : "=r"(d) : "r"(a), "r"(b));
  return d;
}
__device__ __forceinline__ uint4 bf2add4(const uint4& a, const uint4& b) {
  return make_uint4(bf2add(a.x, b.x), bf2add(a.y, b.y), bf2add(a.z, b.z), bf2add(a.w, b.w));
}
__device__ __forceinline__ void sts128(uint32_t a, const uint4& v) {
  asm volatile("st.shared.v4.u32 [%0], {%1,%2,%3,%4};" ::"r"(a), "r"(v.x), "r"(v.y), "r"(v.z), "r"(v.w) : "memory");
}
__device__ __forceinline__ void stmatrix4(uint32_t a, uint32_t r0, uint32_t r1, uint32_t r2, uint32_t r3) {
  asm volatile("stmatrix.sync.aligned.m8n8.x4.shared.b16 [%0], {%1,%2,%3,%4};" ::"r"(a), "r"(r0), "r"(r1), "r"(r2), "r"(r3) : "memory");
}
__device__ __forceinline__ float lds_f32(uint32_t a) {
  float v;
  asm volatile("ld.shared.f32 %0, [%1];" : "=f"(v) : "r"(a) : "memory");
  return v;
}
__device__ __forceinline__ uint32_t packbf(float lo, float hi) {
  uint32_t d;
  asm("cvt.rn.bf16x2.f32 %0, %1, %2;" : "=r"(d) : "f"(hi), "f"(lo));
  return d;
}
__device__ __forceinline__ float bf_lo(uint32_t w) { return __uint_as_float(w << 16); }
__device__ __forceinline__ float bf_hi(uint32_t w) { return __uint_as_float(w & 0xFFFF0000u); }
__device__ __forceinline__ float ex2(float x) {
  float y;
  asm("ex2.approx.ftz.f32 %0, %1;" : "=f"(y) : "f"(x));
  return y;
}
__device__ __forceinline__ uint32_t hfma2(uint32_t a, uint32_t b, uint32_t c) {
  uint32_t d;
  asm("fma.rn.f16x2 %0, %1, %2, %3;" : "=r"(d) : "r"(a), "r"(b), "r"(c));
  return d;
}
__device__ __forceinline__ uint32_t prmt(uint32_t a, uint32_t b, uint32_t s) {
  uint32_t d;
  asm("prmt.b32 %0, %1, %2, %3;" : "=r"(d) : "r"(a), "r"(b), "r"(s));
  return d;
}
__device__ __forceinline__ void hmma(float* c, uint32_t a0, uint32_t a1, uint32_t a2, uint32_t a3, uint32_t b0, uint32_t b1) {
  asm volatile("mma.sync.aligned.m16n8k16.row.col.f32.bf16.bf16.f32 {%0,%1,%2,%3}, {%4,%5,%6,%7}, {%8,%9}, {%0,%1,%2,%3};"
               : "+f"(c[0]), "+f"(c[1]), "+f"(c[2]), "+f"(c[3])
               : "r"(a0), "r"(a1), "r"(a2), "r"(a3), "r"(b0), "r"(b1));
}

template <int TB>
__device__ __forceinline__ void mma_ss_n16(float* d, uint64_t a, uint64_t b, int acc) {
  asm volatile("{.reg .pred p; setp.ne.b32 p, %10, 0;\n"
               "wgmma.mma_async.sync.aligned.m64n16k16.f32.bf16.bf16 {%0,%1,%2,%3,%4,%5,%6,%7}, %8, %9, p, 1, 1, 0, %11;}"
               : "+f"(d[0]), "+f"(d[1]), "+f"(d[2]), "+f"(d[3]), "+f"(d[4]), "+f"(d[5]), "+f"(d[6]), "+f"(d[7])
               : "l"(a), "l"(b), "r"(acc), "n"(TB));
}
template <int TB>
__device__ __forceinline__ void mma_ss_n32(float* d, uint64_t a, uint64_t b, int acc) {
  asm volatile("{.reg .pred p; setp.ne.b32 p, %18, 0;\n"
               "wgmma.mma_async.sync.aligned.m64n32k16.f32.bf16.bf16 {%0,%1,%2,%3,%4,%5,%6,%7,%8,%9,%10,%11,%12,%13,%14,%15}, %16, %17, p, 1, 1, 0, %19;}"
               : "+f"(d[0]), "+f"(d[1]), "+f"(d[2]), "+f"(d[3]), "+f"(d[4]), "+f"(d[5]), "+f"(d[6]), "+f"(d[7]), "+f"(d[8]), "+f"(d[9]), "+f"(d[10]), "+f"(d[11]), "+f"(d[12]), "+f"(d[13]), "+f"(d[14]), "+f"(d[15])
               : "l"(a), "l"(b), "r"(acc), "n"(TB));
}
template <int TB>
__device__ __forceinline__ void mma_ss_n64(float* d, uint64_t a, uint64_t b, int acc) {
  asm volatile("{.reg .pred p; setp.ne.b32 p, %34, 0;\n"
               "wgmma.mma_async.sync.aligned.m64n64k16.f32.bf16.bf16 {%0,%1,%2,%3,%4,%5,%6,%7,%8,%9,%10,%11,%12,%13,%14,%15,%16,%17,%18,%19,%20,%21,%22,%23,%24,%25,%26,%27,%28,%29,%30,%31}, %32, %33, p, 1, 1, 0, %35;}"
               : "+f"(d[0]), "+f"(d[1]), "+f"(d[2]), "+f"(d[3]), "+f"(d[4]), "+f"(d[5]), "+f"(d[6]), "+f"(d[7]), "+f"(d[8]), "+f"(d[9]), "+f"(d[10]), "+f"(d[11]), "+f"(d[12]), "+f"(d[13]), "+f"(d[14]), "+f"(d[15]), "+f"(d[16]), "+f"(d[17]), "+f"(d[18]), "+f"(d[19]), "+f"(d[20]), "+f"(d[21]), "+f"(d[22]), "+f"(d[23]), "+f"(d[24]), "+f"(d[25]), "+f"(d[26]), "+f"(d[27]), "+f"(d[28]), "+f"(d[29]), "+f"(d[30]), "+f"(d[31])
               : "l"(a), "l"(b), "r"(acc), "n"(TB));
}
template <int TB>
__device__ __forceinline__ void mma_ss_n112(float* d, uint64_t a, uint64_t b, int acc) {
  asm volatile("{.reg .pred p; setp.ne.b32 p, %58, 0;\n"
               "wgmma.mma_async.sync.aligned.m64n112k16.f32.bf16.bf16 {%0,%1,%2,%3,%4,%5,%6,%7,%8,%9,%10,%11,%12,%13,%14,%15,%16,%17,%18,%19,%20,%21,%22,%23,%24,%25,%26,%27,%28,%29,%30,%31,%32,%33,%34,%35,%36,%37,%38,%39,%40,%41,%42,%43,%44,%45,%46,%47,%48,%49,%50,%51,%52,%53,%54,%55}, %56, %57, p, 1, 1, 0, %59;}"
               : "+f"(d[0]), "+f"(d[1]), "+f"(d[2]), "+f"(d[3]), "+f"(d[4]), "+f"(d[5]), "+f"(d[6]), "+f"(d[7]), "+f"(d[8]), "+f"(d[9]), "+f"(d[10]), "+f"(d[11]), "+f"(d[12]), "+f"(d[13]), "+f"(d[14]), "+f"(d[15]), "+f"(d[16]), "+f"(d[17]), "+f"(d[18]), "+f"(d[19]), "+f"(d[20]), "+f"(d[21]), "+f"(d[22]), "+f"(d[23]), "+f"(d[24]), "+f"(d[25]), "+f"(d[26]), "+f"(d[27]), "+f"(d[28]), "+f"(d[29]), "+f"(d[30]), "+f"(d[31]), "+f"(d[32]), "+f"(d[33]), "+f"(d[34]), "+f"(d[35]), "+f"(d[36]), "+f"(d[37]), "+f"(d[38]), "+f"(d[39]), "+f"(d[40]), "+f"(d[41]), "+f"(d[42]), "+f"(d[43]), "+f"(d[44]), "+f"(d[45]), "+f"(d[46]), "+f"(d[47]), "+f"(d[48]), "+f"(d[49]), "+f"(d[50]), "+f"(d[51]), "+f"(d[52]), "+f"(d[53]), "+f"(d[54]), "+f"(d[55])
               : "l"(a), "l"(b), "r"(acc), "n"(TB));
}
template <int TB>
__device__ __forceinline__ void mma_ss_n128(float* d, uint64_t a, uint64_t b, int acc) {
  asm volatile("{.reg .pred p; setp.ne.b32 p, %66, 0;\n"
               "wgmma.mma_async.sync.aligned.m64n128k16.f32.bf16.bf16 {%0,%1,%2,%3,%4,%5,%6,%7,%8,%9,%10,%11,%12,%13,%14,%15,%16,%17,%18,%19,%20,%21,%22,%23,%24,%25,%26,%27,%28,%29,%30,%31,%32,%33,%34,%35,%36,%37,%38,%39,%40,%41,%42,%43,%44,%45,%46,%47,%48,%49,%50,%51,%52,%53,%54,%55,%56,%57,%58,%59,%60,%61,%62,%63}, %64, %65, p, 1, 1, 0, %67;}"
               : "+f"(d[0]), "+f"(d[1]), "+f"(d[2]), "+f"(d[3]), "+f"(d[4]), "+f"(d[5]), "+f"(d[6]), "+f"(d[7]), "+f"(d[8]), "+f"(d[9]), "+f"(d[10]), "+f"(d[11]), "+f"(d[12]), "+f"(d[13]), "+f"(d[14]), "+f"(d[15]), "+f"(d[16]), "+f"(d[17]), "+f"(d[18]), "+f"(d[19]), "+f"(d[20]), "+f"(d[21]), "+f"(d[22]), "+f"(d[23]), "+f"(d[24]), "+f"(d[25]), "+f"(d[26]), "+f"(d[27]), "+f"(d[28]), "+f"(d[29]), "+f"(d[30]), "+f"(d[31]), "+f"(d[32]), "+f"(d[33]), "+f"(d[34]), "+f"(d[35]), "+f"(d[36]), "+f"(d[37]), "+f"(d[38]), "+f"(d[39]), "+f"(d[40]), "+f"(d[41]), "+f"(d[42]), "+f"(d[43]), "+f"(d[44]), "+f"(d[45]), "+f"(d[46]), "+f"(d[47]), "+f"(d[48]), "+f"(d[49]), "+f"(d[50]), "+f"(d[51]), "+f"(d[52]), "+f"(d[53]), "+f"(d[54]), "+f"(d[55]), "+f"(d[56]), "+f"(d[57]), "+f"(d[58]), "+f"(d[59]), "+f"(d[60]), "+f"(d[61]), "+f"(d[62]), "+f"(d[63])
               : "l"(a), "l"(b), "r"(acc), "n"(TB));
}
template <int TB>
__device__ __forceinline__ void mma_rs_n32(float* d, const uint32_t* a, uint64_t b, int acc) {
  asm volatile("{.reg .pred p; setp.ne.b32 p, %21, 0;\n"
               "wgmma.mma_async.sync.aligned.m64n32k16.f32.bf16.bf16 {%0,%1,%2,%3,%4,%5,%6,%7,%8,%9,%10,%11,%12,%13,%14,%15}, {%16,%17,%18,%19}, %20, p, 1, 1, %22;}"
               : "+f"(d[0]), "+f"(d[1]), "+f"(d[2]), "+f"(d[3]), "+f"(d[4]), "+f"(d[5]), "+f"(d[6]), "+f"(d[7]), "+f"(d[8]), "+f"(d[9]), "+f"(d[10]), "+f"(d[11]), "+f"(d[12]), "+f"(d[13]), "+f"(d[14]), "+f"(d[15])
               : "r"(a[0]), "r"(a[1]), "r"(a[2]), "r"(a[3]), "l"(b), "r"(acc), "n"(TB));
}
template <int TB>
__device__ __forceinline__ void mma_rs_n64(float* d, const uint32_t* a, uint64_t b, int acc) {
  asm volatile("{.reg .pred p; setp.ne.b32 p, %37, 0;\n"
               "wgmma.mma_async.sync.aligned.m64n64k16.f32.bf16.bf16 {%0,%1,%2,%3,%4,%5,%6,%7,%8,%9,%10,%11,%12,%13,%14,%15,%16,%17,%18,%19,%20,%21,%22,%23,%24,%25,%26,%27,%28,%29,%30,%31}, {%32,%33,%34,%35}, %36, p, 1, 1, %38;}"
               : "+f"(d[0]), "+f"(d[1]), "+f"(d[2]), "+f"(d[3]), "+f"(d[4]), "+f"(d[5]), "+f"(d[6]), "+f"(d[7]), "+f"(d[8]), "+f"(d[9]), "+f"(d[10]), "+f"(d[11]), "+f"(d[12]), "+f"(d[13]), "+f"(d[14]), "+f"(d[15]), "+f"(d[16]), "+f"(d[17]), "+f"(d[18]), "+f"(d[19]), "+f"(d[20]), "+f"(d[21]), "+f"(d[22]), "+f"(d[23]), "+f"(d[24]), "+f"(d[25]), "+f"(d[26]), "+f"(d[27]), "+f"(d[28]), "+f"(d[29]), "+f"(d[30]), "+f"(d[31])
               : "r"(a[0]), "r"(a[1]), "r"(a[2]), "r"(a[3]), "l"(b), "r"(acc), "n"(TB));
}

__device__ __forceinline__ float rcp(float x) {
  float y;
  asm("rcp.approx.ftz.f32 %0, %1;" : "=f"(y) : "f"(x));
  return y;
}
__device__ __forceinline__ uint32_t exp2_pair_fma(float s0, float s1) {
  const uint32_t a0 = __float_as_uint(s0), a1 = __float_as_uint(s1);
  const uint32_t m = prmt(a0, a1, 0x7531), e = prmt(a0, a1, 0xF6B2);
  const uint32_t u = hfma2(m, 0x2d712d71u, 0xb41cb41cu);
  const uint32_t w = hfma2(u, u, 0x21a421a4u);
  const uint32_t p = hfma2(w, u, 0x1f791f79u);
  return e * 128u + p;
}
template <int G, int MASK>
__device__ __forceinline__ void exp_groups(const float* S, uint32_t* P) {
#pragma unroll
  for (int g = 0; g < G; g++) {
    if ((MASK >> g) & 1) {
      P[2 * g] = exp2_pair_fma(S[4 * g], S[4 * g + 1]);
      P[2 * g + 1] = exp2_pair_fma(S[4 * g + 2], S[4 * g + 3]);
    } else {
      P[2 * g] = packbf(ex2(S[4 * g]), ex2(S[4 * g + 1]));
      P[2 * g + 1] = packbf(ex2(S[4 * g + 2]), ex2(S[4 * g + 3]));
    }
  }
}
__device__ __forceinline__ void qk_mma(float* S, uint64_t dq, uint64_t dk) {
  mma_ss_n64<0>(S, dq, dk, 0);
  mma_ss_n64<0>(S, dq + 2, dk + 2, 1);
}
__device__ __forceinline__ void pv_mma(float* O, const uint32_t* P, uint64_t dv) {
#pragma unroll
  for (int t = 0; t < 4; t++) mma_rs_n32<1>(O, P + 4 * t, dv + t * 64, 1);
}

template <int MASK>
__device__ __forceinline__ void attn_step(float* S, float* O, uint32_t* Pin, uint32_t* Pout, uint64_t dq, uint64_t dk, uint64_t dv,
                                          uint32_t arr, uint32_t bar, uint32_t parity, bool use_arr, bool use_bar) {
  wg_fence();
  qk_mma(S, dq, dk);
  wg_commit();
  pv_mma(O, Pin, dv);
  wg_commit();
  wg_wait<1>();
  pin<32>(S);
  uint32_t ok = 1;
  if (use_arr) asm volatile("{.reg .pred p; setp.ne.u32 p, %0, 0; @p mbarrier.arrive.shared::cta.b64 _, [%0];}" ::"r"(arr) : "memory");
  if (use_bar) ok = mbar_try(bar, parity);
  exp_groups<8, MASK>(S, Pout);
  pin<16>(Pout);
  if (use_bar) mbar_finish(ok, bar, parity);
  wg_wait<0>();
}

__device__ __forceinline__ void kv_wait(int i, unsigned need, unsigned epoch, unsigned& ready, int lane) {
  const unsigned* flag = &g_kvflag[(((i >> 2) * 2 + lane) & 15) * 32];
  for (int it = 0; (ready & need) != need; it++) {
    bool set = false;
    if (POLL_ALL || (((need & ~ready) >> lane) & 1)) set = (int)(ld_acquire(flag) - 8 * epoch) >= 0;
    ready |= __ballot_sync(0xffffffffu, set);
    fence_async_global();
    if (POLL_SLEEP && (ready & need) != need) __nanosleep(POLL_SLEEP);
    SPIN_LIMIT(it, 3000)
  }
}
__device__ __forceinline__ void kv_load(int i, int n) {
  const uint32_t sb = smem_base();
  const int ps = (2 + n) % 3;
  const uint4* src = &g_s.kv[(((i >> 2) + n) & 7) * 2048];
  mbar_wait_idle(sb + BAR_KVE + ps * 8, (ps < 2 ? (n - 1) / 3 : n / 3 - 1) & 1);
  if (elect()) {
    mbar_expect(sb + BAR_KVF + ps * 8, 32768);
    bulk_load(sb + ps * 32768, src, 32768, sb + BAR_KVF + ps * 8);
  }
  __syncwarp();
}
__device__ __forceinline__ void arm_exchange(int i, int j, int pw, int lane) {
  const uint4 s4 = make_uint4(SENTINEL, SENTINEL, SENTINEL, SENTINEL);
  uint4* po = g_o + i * 4096 + j * 1024 + pw * 32 + lane;
  uint4* ph = g_h + i * 4096 + (pw * 16 + (lane >> 4)) * 64 + j * 16 + (lane & 15);
  bar_sync(8, 128);
#pragma unroll
  for (int k = 0; k < 8; k++) {
    po[k * 128] = s4;
    if ((lane & 15) < 14) ph[k * 128] = s4;
  }
  if (pw == 1) bar_sync(11, 128); else bar_arrive(11, 128);
}
__device__ __forceinline__ bool scores_unbounded(int lane) {
  const uint32_t sb = smem_base();
  mbar_wait_idle(sb + BAR_KM, 0);
  const uint4 ka = lds128(sb + OFF_KMAX + lane * 16);
  const uint32_t k2 = __vmaxu2(__vmaxu2(ka.x, ka.y), __vmaxu2(ka.z, ka.w));
  const float qm = __uint_as_float(__reduce_max_sync(0xffffffffu, lds32(sb + OFF_QMAX + (lane & 7) * 4)));
  const float kk = __uint_as_float(__reduce_max_sync(0xffffffffu, k2 << 16)) + __uint_as_float(__reduce_max_sync(0xffffffffu, k2 & 0xFFFF0000u));
  return !(qm * kk <= SCORE_BOUND * SCORE_BOUND);
}

__device__ __forceinline__ void wq_load(int j, const CUtensorMap* tm, int q0, int q1) {
  const uint32_t sb = smem_base();
#pragma unroll 1
  for (int q = q0; q < q1; q++) {
    mbar_expect(sb + BAR_WQ + q * 8, 2 * 14336);
    tma2d(sb + OFF_C + q * 14336, tm, j * 112, q * 112, sb + BAR_WQ + q * 8);
    tma2d(sb + OFF_C + 57344 + q * 14336, tm, j * 112 + 56, q * 112, sb + BAR_WQ + q * 8);
  }
}
template <int G>
__device__ __forceinline__ float max_row_norm2(const uint32_t* w, uint32_t zero) {
  float n[2] = {0.f, 0.f};
#pragma unroll
  for (int k = 0; k < 2 * G; k++) {
    const float lo = __uint_as_float(w[k] << (16 + zero)), hi = __uint_as_float(w[k] & (0xFFFF0000u | zero));
    n[k & 1] = fmaf(lo, lo, fmaf(hi, hi, n[k & 1]));
  }
  n[0] += __shfl_xor_sync(0xffffffffu, n[0], 1); n[1] += __shfl_xor_sync(0xffffffffu, n[1], 1);
  n[0] += __shfl_xor_sync(0xffffffffu, n[0], 2); n[1] += __shfl_xor_sync(0xffffffffu, n[1], 2);
  const float m = (n[0] == n[0] && n[1] == n[1]) ? fmaxf(n[0], n[1]) : __int_as_float(0x7f800000);
  return __uint_as_float(__reduce_max_sync(0xffffffffu, __float_as_uint(m)));
}

__device__ __forceinline__ float rstd_of(float sum_sq, float dm) { return rsqrtf(fmaxf(sum_sq * (1.0f / DM) - dm * dm, 0.f) + 1e-5f); }
template <int N, bool VAR, class F>
__device__ __forceinline__ void center_rows(uint4* v, uint32_t sb, int row, int c, bool odd, F where) {
  constexpr uint32_t ONES = 0x3F803F80u;
  float s[2][4] = {}, q[2][4] = {};
#pragma unroll
  for (int t = 0; t < N; t++) hmma(s[t & 1], v[t].x, v[t].y, v[t].z, v[t].w, ONES, ONES);
  float sum = (s[0][0] + s[0][2]) + (s[1][0] + s[1][2]);
  sum += __shfl_xor_sync(0xffffffffu, sum, 4);
  const float mean = sum * (1.0f / DM);
  const uint32_t nm = packbf(-mean, -mean), nmo = odd ? nm : 0u;
#pragma unroll
  for (int t = 0; t < N; t++) {
    const uint32_t m = (t & 1) ? nmo : nm;
    v[t] = bf2add4(v[t], make_uint4(m, m, m, m));
    if (!(t & 1) || odd) sts128(sb + OFF_A + (row & 7) * 128 + where(t), v[t]);
    if (VAR) hmma(q[t & 1], bf2mul(v[t].x, v[t].x), bf2mul(v[t].y, v[t].y), bf2mul(v[t].z, v[t].z), bf2mul(v[t].w, v[t].w), ONES, ONES);
  }
  float r = mean + bf_lo(nm);
  if (VAR) {
    float d = (q[0][0] + q[0][2]) + (q[1][0] + q[1][2]);
    d += __shfl_xor_sync(0xffffffffu, d, 4);
    r = rstd_of(d, r);
  }
  if (c == 0) sts32(sb + OFF_RSTD + row * 4, __float_as_uint(r));
  fence_async_smem();
}
template <int N>
__device__ __forceinline__ void row_rstd(const uint4* v, uint32_t sb, int row, int lane) {
  const float dm = lds_f32(sb + OFF_RSTD + row * 4);
  float q[4] = {0.f, 0.f, 0.f, 0.f};
#pragma unroll
  for (int t = 0; t < N; t++) {
    const uint4 u = v ? v[t] : lds128(sb + OFF_A + t * 8192 + row * 128 + ((lane & 7) << 4));
    q[0] = fmaf(bf_lo(u.x), bf_lo(u.x), fmaf(bf_hi(u.x), bf_hi(u.x), q[0]));
    q[1] = fmaf(bf_lo(u.y), bf_lo(u.y), fmaf(bf_hi(u.y), bf_hi(u.y), q[1]));
    q[2] = fmaf(bf_lo(u.z), bf_lo(u.z), fmaf(bf_hi(u.z), bf_hi(u.z), q[2]));
    q[3] = fmaf(bf_lo(u.w), bf_lo(u.w), fmaf(bf_hi(u.w), bf_hi(u.w), q[3]));
  }
  float d = (q[0] + q[1]) + (q[2] + q[3]);
  d += __shfl_xor_sync(0xffffffffu, d, 1);
  d += __shfl_xor_sync(0xffffffffu, d, 2);
  d += __shfl_xor_sync(0xffffffffu, d, 4);
  if ((lane & 7) == 0) sts32(sb + OFF_RSTD + row * 4, __float_as_uint(rstd_of(d, dm)));
  __syncwarp();
  if (lane == 0) mbar_arrive(sb + BAR_RSTD);
}

__device__ const uint32_t g_seq[8 * 20] = {
    0x401009, 0x44104e, 0x4090b4, 0x448129, 0x1c88170, 0x34c81f6, 0x5e18270, 0x76582f4, 0x9d60390, 0x50a402, 0xd548458, 0xf5c84d2, 0x11d9056e, 0x147385f4, 0x0, 0x0, 0x0, 0x0, 0x0, 0x0,
    0x42102b, 0x461070, 0x4a10d6, 0xc1018b, 0x24a81b2, 0x445021a, 0x64b028b, 0x850031a, 0xb5803b6, 0x5124e4, 0xdd6846e, 0xfd30514, 0x125b0590, 0x14f5861a, 0x0, 0x0, 0x0, 0x0, 0x0, 0x0,
    0x67d32d, 0x481092, 0x4290f8, 0x146814e, 0x2c301d4, 0x3c70238, 0x6e382b2, 0x8d20358, 0xada03d2, 0x77e626, 0xe588490, 0x10d5053a, 0x12dd05b6, 0x0, 0x0, 0x0, 0x0, 0x0, 0x0, 0x0,
    0x0, 0x0, 0x4c111a, 0x549024e, 0x7cd02d6, 0x954036e, 0xbdc03f4, 0xc52843a, 0xeda84b6, 0x11570558, 0x137185d2, 0x0, 0x0, 0x0, 0x0, 0x0, 0x0, 0x0, 0x0, 0x0,
    0x809, 0x82b, 0x84e, 0x870, 0x892, 0x8d6, 0x91a, 0x0, 0xb1a, 0xb58, 0xb6e, 0xb90, 0xbb6, 0xbd2, 0xbf4, 0x0, 0x0, 0x0, 0x0, 0x0,
    0x8b4, 0x8f8, 0x129, 0x94e, 0x970, 0x9b2, 0x9f6, 0x0, 0x402, 0xc3a, 0xc58, 0xc6e, 0xc90, 0xcb6, 0xcd2, 0x0, 0x0, 0x0, 0x0, 0x0,
    0x98b, 0x9d4, 0xa1a, 0xa38, 0xa4e, 0x28b, 0xad6, 0x0, 0x4e4, 0xd14, 0xd3a, 0x558, 0x56e, 0x590, 0x5b6, 0x0, 0x0, 0x0, 0x0, 0x0,
    0xa70, 0xab2, 0xaf4, 0x32d, 0x0, 0x0, 0x0, 0x0, 0x5d2, 0x5f4, 0x61a, 0x626, 0x0, 0x0, 0x0, 0x0, 0x0, 0x0, 0x0, 0x0};

struct FfnLoad {
  uint32_t dst, bar, gate, boxes;
  int col, row, col2, row2;
  const CUtensorMap* tm;
};
__device__ __forceinline__ FfnLoad ffn_decode(uint32_t e, int j, const CUtensorMap* tm_w1, const CUtensorMap* tm_w2) {
  const uint32_t sb = smem_base();
  const bool half = (e >> 14) & 1, second = (e >> 20) & 1, narrow = (e >> 21) & 1;
  const int kind = (e >> 12) & 3;
  FfnLoad f;
  f.col = ((e >> 15) & 3) * 128 + (second ? 0 : j * 448);
  f.row = (((e >> 17) & 7) << (narrow ? 7 : 6)) + (second ? j * 448 : 0);
  f.col2 = f.col + (narrow ? 0 : 64);
  f.row2 = f.row + (narrow ? 64 : 0);
  f.tm = second ? tm_w2 : tm_w1;
  f.dst = sb + (e & 31) * 8192;
  f.bar = sb + BAR_RF + ((e >> 5) & 63) * 8;
  f.gate = sb + (kind == 0 ? BAR_FREE + (e >> 23) * 8 : kind == 2 ? BAR_F1 : BAR_WO);
  f.boxes = !(e >> 22) ? 0 : half ? 1 : 2;
  if (f.boxes) mbar_expect(f.bar, f.boxes * 8192);
  return f;
}
__device__ __forceinline__ void ffn_load(const FfnLoad& f) {
  mbar_wait_lane(f.gate);
  TS2((f.bar - smem_base() - BAR_RF) / 8, 0);
  tma2d(f.dst, f.tm, f.col, f.row, f.bar);
  if (f.boxes == 2) tma2d(f.dst + 8192, f.tm, f.col2, f.row2, f.bar);
}
struct FfnStages {
  uint32_t desc, full, gate, release;
};
__device__ __forceinline__ FfnStages ffn_stages(uint32_t e, int l, bool narrow, bool lead_warp) {
  const uint32_t sb = smem_base();
  const int t = l & 7;
  FfnStages s;
  s.desc = (uint32_t)mkdesc(sb + (e & 31) * 8192, 8192, 1024, 1);
  s.full = sb + BAR_RF + ((e >> 5) & 63) * 8;
  s.gate = sb + ((l & 8) && e && (narrow || !(t & 1)) ? BAR_H1 + (narrow ? t : t >> 1) * 8 : BAR_WO);
  s.release = lead_warp && (e >> 11) ? sb + BAR_FREE + ((e >> 5) & 63) * 8 : 0u;
  return s;
}
__device__ __forceinline__ uint64_t desc128(uint32_t lo) {
  uint64_t d;
  asm("mov.b64 %0, {%1, %2};" : "=l"(d) : "r"(lo), "r"(0x40000040u));
  return d;
}
__device__ __forceinline__ void arrive_if(uint32_t bar, bool lane0) {
  asm volatile("{.reg .pred p; setp.ne.u32 p, %1, 0; @p mbarrier.arrive.shared::cta.b64 _, [%0];}" ::"r"(bar), "r"(lane0 ? bar : 0u) : "memory");
}
template <bool NARROW>
__device__ __forceinline__ void ffn_chunk(float* acc, const FfnStages& s, int pass, bool lane0, bool first) {
  const int l0 = __shfl_sync(0xffffffffu, 8 * pass, 0);
  uint32_t alo = (uint32_t)mkdesc(smem_base(), 16, 1024, 1) + l0 * (OFF_B / 128);
  uint32_t held = 0, blo = __shfl_sync(0xffffffffu, s.desc, l0);
  mbar_wait_idle(__shfl_sync(0xffffffffu, s.gate, l0), 0);
  mbar_wait_idle(__shfl_sync(0xffffffffu, s.full, l0), 0);
  if (first) bar_sync(2, 640);
  TS(24 + pass);
  pin<64>(acc);
#pragma unroll 1
  for (int l = l0; l < l0 + (NARROW ? 4 : 7); l++) {
    const uint64_t a = desc128(alo), b = desc128(__shfl_sync(0xffffffffu, blo, 0));
    wg_fence();
    if (NARROW) {
      mma_ss_n64<1>(acc, a, b, l > l0);
      mma_ss_n64<1>(acc, a + 2, b + 128, 1);
    } else {
      mma_ss_n128<1>(acc, a, b, l > l0);
    }
    const uint32_t rn = __shfl_sync(0xffffffffu, s.full, l + 1), hn = __shfl_sync(0xffffffffu, s.gate, l + 1);
    const uint32_t rel = __shfl_sync(0xffffffffu, s.release, l);
    blo = __shfl_sync(0xffffffffu, s.desc, l + 1);
    const uint32_t ok = mbar_try(rn, 0) & mbar_try(hn, 0);
    if (NARROW) {
      mma_ss_n64<1>(acc, a + 4, b + 256, 1);
      mma_ss_n64<1>(acc, a + 6, b + 384, 1);
      wg_commit();
      if (l < l0 + 3) {
        wg_fence();
#pragma unroll
        for (int k = 0; k < 4; k++) mma_ss_n64<1>(acc, a + 512 + k * 2, b + 512 + k * 128, 1);
        wg_commit();
      }
    } else {
#pragma unroll
      for (int k = 1; k < 4; k++) mma_ss_n128<1>(acc, a + k * 2, b + k * 128, 1);
      wg_commit();
    }
    wg_wait<1>();
    arrive_if(held, lane0);
    held = rel;
    mbar_finish2(ok, rn, hn);
    if ((threadIdx.x & 96) == 0) TS2((rn - smem_base() - BAR_RF) / 8, 2);
    alo += NARROW ? 1024 : 512;
  }
  wg_wait<0>();
  pin<64>(acc);
  arrive_if(held, lane0);
}

__device__ __forceinline__ float gelu_half(float h) {
  const float u = h * fmaf(h * h, 8.0f * 0.0356774081f, 2.0f * 0.7978845608f);
  float t;
  asm("tanh.approx.f32 %0, %1;" : "=f"(t) : "f"(u));
  return fmaf(h, t, h);
}
__device__ __forceinline__ void scale_bias(float* acc, const float* src, uint32_t bias, float r0, float r1) {
#pragma unroll
  for (int g = 0; g < 8; g++) {
    const uint32_t b = lds32(bias + g * 16);
    acc[4 * g] = fmaf(src[4 * g], r0, bf_lo(b));
    acc[4 * g + 1] = fmaf(src[4 * g + 1], r0, bf_hi(b));
    acc[4 * g + 2] = fmaf(src[4 * g + 2], r1, bf_lo(b));
    acc[4 * g + 3] = fmaf(src[4 * g + 3], r1, bf_hi(b));
  }
}

struct Params {
  const __nv_bfloat16 *x, *wq, *wk, *wv, *wo, *w1, *b1, *w2, *b2;
  __nv_bfloat16* out;
};

__device__ __forceinline__ void post_attention(float* O, int warp, const Params& p, const CUtensorMap* tm_out) {
  const uint32_t sb = smem_base();
  int tid;
  asm volatile("mov.u32 %0, %%tid.x;" : "=r"(tid));
  const int lane = tid & 31, wg = warp >> 2, wl = warp & 3, q4 = lane & 3, j = cta_j(), i = cta_i();
  const int row = warp * 4 + (lane >> 3), c8 = lane & 7;
  const int mrow = wl * 16 + (lane & 7) + ((lane >> 3) & 1) * 8, mg = lane >> 4;
  uint32_t stages;
  {
    const float i0 = rcp(__shfl_sync(0xffffffffu, O[12], (lane & 28) | 2)), i1 = rcp(__shfl_sync(0xffffffffu, O[14], (lane & 28) | 2));
    const uint4 f0 = make_uint4(packbf(O[0] * i0, O[1] * i0), packbf(O[2] * i1, O[3] * i1), packbf(O[4] * i0, O[5] * i0), packbf(O[6] * i1, O[7] * i1));
    const uint4 f1 = make_uint4(packbf(O[8] * i0, O[9] * i0), packbf(O[10] * i1, O[11] * i1),
                                q4 < 2 ? packbf(O[12] * i0, O[13] * i0) : 0u, q4 < 2 ? packbf(O[14] * i1, O[15] * i1) : 0u);
    const uint32_t frag = mrow * 64 + ((mg ^ ((mrow >> 1) & 3)) << 4);
    stmatrix4(sb + OFF_Q + wg * 4096 + frag, f0.x, f0.y, f0.z, f0.w);
    stmatrix4(sb + OFF_Q + wg * 4096 + (frag ^ 32), f1.x, f1.y, f1.z, f1.w);
    if (FENCE_FIRST) fence_async_smem();
    st_relaxed4(g_o + i * 4096 + (j * 4 + wg) * 256 + (tid & 127), f0);
    st_relaxed4(g_o + i * 4096 + (j * 4 + wg) * 256 + 128 + (tid & 127), f1);
    if (!FENCE_FIRST) fence_async_smem();
    TS(26);
    TSG(88);
    bar_sync(1, 512);
    uint4 v[8];
    const uint4* op[8];
#pragma unroll
    for (int m = 0; m < 8; m++) op[m] = g_o + i * 4096 + ((j + wg) & 3) * 1024 + (tid & 127) + 128 * m;
    if (OSEQ == 1 && wg >= 2) bar_sync(7 + wg, 256);
    if (OSEQ > 1 && wg >= 2) __nanosleep(OSEQ * (wg - 1));
#pragma unroll
    for (int m = 0; m < 8; m++)
      if (wg != 0) v[m] = ld_relaxed4(op[m]);
    if (OSEQ == 1 && (wg == 1 || wg == 2)) bar_arrive(8 + wg, 256);
    const bool odd = c8 < 6;
    uint4 hv[8] = {}, br[2] = {};
    uint4* hp0 = g_h + i * 4096 + row * 64 + c8;
    uint32_t stg = sb + OFF_B + row * 224 + c8 * 16;
    asm volatile("" : "+l"(hp0), "+r"(stg));
    auto load_residual = [&]() {
#pragma unroll
      for (int u = 0; u < 2; u++) {
        ld_relaxed4_if(hv[u], reinterpret_cast<const uint4*>(p.x + (size_t)(i * 64 + row) * DM) + j * 14 + c8 + 8 * u, !u || odd);
        ld_relaxed4_if(br[u], reinterpret_cast<const uint4*>(p.b2) + j * 14 + c8 + 8 * u, !u || odd);
      }
      asm volatile("ld.relaxed.gpu.global.u32 %0, [%1];" : "=r"(stages) : "l"(&g_seq[(4 + wg) * 20 + (lane & 15)]) : "memory");
    };
    constexpr uint32_t STG = OFF_B;
    if (wg == 0) {
      float acc[56];
      pin<56>(acc);
      const uint64_t dq = mkdesc(sb + OFF_Q, 16, 512, 2), da = mkdesc(sb, 16, 512, 2) - 1024, db = mkdesc(sb + OFF_C, 1024, 256, 3);
      mbar_wait(sb + BAR_WO, 0);
      if (XW0 == 1) load_residual();
      wg_fence();
#pragma unroll
      for (int s = 0; s < 8; s++) mma_ss_n112<1>(acc, dq + ((s >> 1) * 4096 + (s & 1) * 32) / 16, db + ((s >> 1) * 7168 + (s & 1) * 512) / 16, s > 0);
      wg_commit();
      wg_wait<0>();
      pin<56>(acc);
      TS(6);
      if (EA_EARLY) bar_arrive(8, 256);
#pragma unroll
      for (int u = 1; u < 4; u++) {
        bar_sync(12 + u, 256);
        if (u == 3) TS(22);
        if (u == 1 && XW0 == 0) load_residual();
        if (u == 3 && !EA_EARLY) bar_arrive(8, 256);
        wg_fence();
#pragma unroll
        for (int s = 8 * u; s < 8 * u + 8; s++)
          mma_ss_n112<1>(acc, da + ((s >> 1) * 4096 + (s & 1) * 32) / 16, db + ((s >> 1) * 7168 + (s & 1) * 512) / 16, 1);
        wg_commit();
        if (u == 2) {
          wg_wait<1>();
          if (lane == 0) mbar_arrive(sb + BAR_WH);
        }
      }
      wg_wait<0>();
      pin<56>(acc);
      TS(7);
#pragma unroll
      for (int g = 0; g < 14; g += 2) {
        const float* a = acc + 4 * g;
        stmatrix4(sb + STG + mrow * 224 + (g + mg) * 16, packbf(a[0], a[1]), packbf(a[2], a[3]), packbf(a[4], a[5]), packbf(a[6], a[7]));
      }
    } else {
      TSG(87);
      poll_chunks<8>(v, op);
      TS(6);
      TSG(89);
#pragma unroll
      for (int m = 0; m < 8; m++) stmatrix4(sb + ((wg - 1) * 4 + (m >> 1)) * 4096 + (frag ^ ((m & 1) * 32)), v[m].x, v[m].y, v[m].z, v[m].w);
      fence_async_smem();
      bar_arrive(12 + wg, 256);
      load_residual();
    }
    bar_sync(1, 512);
    TS(23);
    TSG(94);
    hv[0] = bf2add4(hv[0], lds128(stg));
    if (odd) hv[1] = bf2add4(hv[1], lds128(stg + 128));
    st_relaxed4(hp0 + j * 16, hv[0]);
    if (odd) st_relaxed4(hp0 + j * 16 + 8, hv[1]);
    const uint4* hp[6];
#pragma unroll
    for (int t = 2; t < 8; t++) {
      hp[t - 2] = hp0 + ((j + (t >> 1)) & 3) * 16 + (t & 1) * 8;
      ld_relaxed4_if(hv[t], hp[t - 2], !(t & 1) || odd);
    }
    sts128(stg, bf2add4(hv[0], br[0]));
    if (odd) sts128(stg + 128, bf2add4(hv[1], br[1]));
    poll_chunks<6>(hv + 2, hp);
    bar_arrive(3, 640);
    TS(8);
    TSG(95);
    center_rows<8, false>(hv, sb, row, c8, odd, [&](int t) {
      const int ch = ((j + (t >> 1)) & 3) * 14 + (t & 1) * 8 + c8;
      return (ch >> 3) * 8192 + (row >> 3) * 1024 + (((ch & 7) ^ (row & 7)) << 4);
    });
    if (wg != 0) {
      bar_sync(2, 640);
      TS(9);
      row_rstd<8>(hv, sb, row, lane);
    }
    if (wg == 3) row_rstd<7>(nullptr, sb, row - 48, lane);
  }

  const bool narrow = wg == 3;
  const FfnStages fs = ffn_stages(stages, lane & 15, narrow, wl == 0);
  float acc[64];
#pragma unroll 1
  for (int pass = 0; pass < 2; pass++) {
    if (narrow) ffn_chunk<true>(acc, fs, pass, lane == 0, false);
    else ffn_chunk<false>(acc, fs, pass, lane == 0, wg == 0 && pass == 0);
    if (pass == 0) {
      TS(10);
      if (wl == 0 && lane == 0) mbar_arrive(sb + BAR_F1);
      if (wg == 0) mbar_wait(sb + BAR_OI, 0);
      mbar_wait_idle(sb + BAR_RSTD, 0);
      const float r0 = 0.5f * lds_f32(sb + OFF_RSTD + (wl * 16 + (lane >> 2)) * 4);
      const float r1 = 0.5f * lds_f32(sb + OFF_RSTD + (wl * 16 + 8 + (lane >> 2)) * 4);
      const uint32_t bias = sb + OFF_B1 + wg * 256 + q4 * 4;
#pragma unroll 1
      for (int hf = 0; hf < (narrow ? 1 : 2); hf++) {
        if (hf == 0) scale_bias(acc, acc, bias, r0, r1);
        else scale_bias(acc, acc + 32, bias + 128, r0, r1);
#pragma unroll
        for (int g = 0; g < 8; g += 2) {
          const float* a = acc + 4 * g;
          stmatrix4(sb + OFF_B + (2 * wg + hf) * 8192 + mrow * 128 + (((g + mg) ^ (mrow & 7)) << 4),
                    packbf(gelu_half(a[0]), gelu_half(a[1])), packbf(gelu_half(a[2]), gelu_half(a[3])),
                    packbf(gelu_half(a[4]), gelu_half(a[5])), packbf(gelu_half(a[6]), gelu_half(a[7])));
        }
      }
      fence_async_smem();
      __syncwarp();
      if (lane == 0) mbar_arrive(sb + BAR_H1 + wg * 8);
      TS(11);
    } else {
      TS(12);
#pragma unroll
      for (int hf = 0; hf < 2; hf++) {
        if (hf && narrow) break;
        const uint32_t stage = sb + OFF_A + (2 * wg + hf) * 8192;
#pragma unroll
        for (int g = 0; g < 8; g += 2) {
          const float* a = acc + 32 * hf + 4 * g;
          stmatrix4(stage + mrow * 128 + (((g + mg) ^ (mrow & 7)) << 4), packbf(a[0], a[1]), packbf(a[2], a[3]), packbf(a[4], a[5]), packbf(a[6], a[7]));
        }
        fence_async_smem();
        bar_sync(4 + wg, 128);
        if (wl == 0) {
          if (hf == 0) mbar_wait(sb + BAR_EP, 1);
          if (elect()) {
            fence_async_global();
            asm volatile("cp.reduce.async.bulk.tensor.2d.global.shared::cta.add.tile.bulk_group [%0, {%2,%3}], [%1];"
                         ::"l"(tm_out), "r"(stage), "r"(wg * 128 + hf * 64), "r"(i * 64) : "memory");
            asm volatile("cp.async.bulk.commit_group;" ::: "memory");
          }
          __syncwarp();
        }
      }
      if (RDWAIT) asm volatile("cp.async.bulk.wait_group.read 0;" ::: "memory"); else asm volatile("cp.async.bulk.wait_group 0;" ::: "memory");
      TS(13);
    }
  }
}

}

__global__ void
__launch_bounds__(NTHREADS, 1)
fused_block_kernel(const Params p, const __grid_constant__ CUtensorMap tm_wq, const __grid_constant__ CUtensorMap tm_wo,
                   const __grid_constant__ CUtensorMap tm_w1, const __grid_constant__ CUtensorMap tm_w2,
                   const __grid_constant__ CUtensorMap tm_out, const __grid_constant__ CUtensorMap tm_ini) {
  extern __shared__ __align__(1024) unsigned char smem[];
  const uint32_t sb = smem_base();
  const int tid = threadIdx.x, lane = tid & 31;
  const int j = cta_j(), i = cta_i();

  TS(0);
  if (tid >= 512) {
    asm volatile("setmaxnreg.dec.sync.aligned.u32 32;");
    const int pw = __shfl_sync(0xffffffffu, (tid >> 5) & 3, 0);
    if (elect()) {
#pragma unroll
      for (int k = 0; k < 16; k++) mbar_init(sb + OFF_X + ((3 - pw) * 16 + k) * 8, 1);
      if (pw == 3) {
        asm volatile("fence.mbarrier_init.release.cluster;" ::: "memory");
        mbar_expect(sb + BAR_EP, 16);
        bulk_load(sb + OFF_EPOCH, g_s.epoch, 16, sb + BAR_EP);
        l2_prefetch(reinterpret_cast<const char*>(p.wq) + blockIdx.x * 3136, 3136);
        asm volatile("prefetch.tensormap [%0];" ::"l"(&tm_wq) : "memory");
      }
#pragma unroll
      for (int k = 0; k < 4; k++) mbar_init(sb + OFF_X + (64 + pw * 4 + k) * 8, pw == 3 ? 16 : 4);
#pragma unroll
      for (int k = 0; k < 13; k++) mbar_init(sb + BAR_FREE + (pw * 13 + k) * 8, 1);
    }
    __syncwarp();
    TSP(28);
    const uint32_t acts = __ldg(&g_seq[pw * 20 + lane]);
    if (pw == 3 && WQ_EARLY > 0) {
      __nanosleep(WQ_AT);
      if (elect()) wq_load(j, &tm_wq, 0, WQ_EARLY);
      __syncwarp();
    }
    bar_sync(0, 640);
    if (pw == 3 && elect()) wq_load(j, &tm_wq, WQ_EARLY, WQ_MID);
    __syncwarp();
    mbar_wait(sb + BAR_EP, 0);
    const unsigned epoch = lds32(sb + OFF_EPOCH) + 1;
    if (pw == 0) {
      unsigned ready = 0;
      bool slow = false;
      if (POLL_LATE) bar_sync(11, 192);
#pragma unroll 1
      for (int h = 0; h < 2; h++) {
        kv_wait(i, 1u << h, epoch, ready, lane);
        if (h == 0) TSP(21);
        if (elect()) {
          mbar_expect(sb + BAR_KVF + (3 - h) * 8, 16384);
          bulk_load(sb + 65536 + h * 16384, &g_s.kv[(i >> 2) * 2048 + h * 1024], 16384, sb + BAR_KVF + (3 - h) * 8);
        }
        __syncwarp();
      }
#pragma unroll 1
      for (int n = 1; n < 8; n++) {
        kv_wait(i, n < 3 ? 3u << (2 * n) : 0xFFFFu, epoch, ready, lane);
        if (n == 7) {
          slow = scores_unbounded(lane);
          if (lane == 0) sts32(sb + OFF_SLOW, slow);
          __syncwarp();
        }
        kv_load(i, n);
        if (n == 2) arm_exchange(i, j, pw, lane);
        if (n == 4) {
          for (int it = 0; !__all_sync(0xffffffffu, (int)(ld_acquire(&g_rstflag[lane * 32]) - 4 * epoch) >= 0); it++) { SPIN_LIMIT(it, 1001) }
          fence_async_global();
          if (elect()) {
            mbar_expect(sb + BAR_KM, 512);
            bulk_load(sb + OFF_KMAX, g_kmax, 512, sb + BAR_KM);
          }
          __syncwarp();
        }
      }
      if (slow) {
#pragma unroll 1
        for (int n = 8; n < 16; n++) kv_load(i, n);
      }
    } else if (pw == 1) {
      bar_sync(11, POLL_LATE ? 192 : 160);
      if (lane == 0) publish(&g_kvflag[(i >> 1) * 32]);
      __syncwarp();
      TSP(2);
      if (WQ_MID < 4 && elect()) wq_load(j, &tm_wq, WQ_MID, 4);
      __syncwarp();
      arm_exchange(i, j, pw, lane);
      bar_sync(2, 160);
      if (lane == 0) publish(&g_rstflag[i * 32]);
    } else if (pw == 2) {
#pragma unroll 1
      for (int k = lane; k < 224; k += 32) {
        const uint32_t b = __ldg(reinterpret_cast<const uint32_t*>(p.b1 + j * 448) + k);
        sts32(sb + OFF_B1 + k * 4, packbf(0.5f * bf_lo(b), 0.5f * bf_hi(b)));
      }
      if (lane == 0) {
        asm volatile("prefetch.tensormap [%0];" ::"l"(&tm_wo) : "memory");
        asm volatile("prefetch.tensormap [%0];" ::"l"(&tm_w1) : "memory");
        asm volatile("prefetch.tensormap [%0];" ::"l"(&tm_w2) : "memory");
        asm volatile("prefetch.tensormap [%0];" ::"l"(&tm_out) : "memory");
        asm volatile("prefetch.tensormap [%0];" ::"l"(&tm_ini) : "memory");
        if ((uint32_t)__cvta_generic_to_shared(smem) != sb) __trap();
      }
      __syncwarp();
      arm_exchange(i, j, pw, lane);
      mbar_wait_idle(sb + BAR_KVE, 0);
      if (elect()) {
        mbar_expect(sb + BAR_WO, 16 * 7168);
#pragma unroll 1
        for (int u = 0; u < 8; u++) {
          __nanosleep(1000);
          tma4d(sb + OFF_C + u * 14336, &tm_wo, 0, 0, j * 7, (j * 4 + u * 2) & 15, sb + BAR_WO);
          if (u == 0) {
            l2_prefetch(reinterpret_cast<const char*>(p.w1) + blockIdx.x * 12544, 12544);
            l2_prefetch(reinterpret_cast<const char*>(p.w2) + blockIdx.x * 12544, 12544);
          }
        }
      }
    }
    if (pw == 3) arm_exchange(i, j, pw, lane);
    __syncwarp();
    const FfnLoad f = ffn_decode(lane < 20 ? acts : 0u, j, &tm_w1, &tm_w2);
    __syncwarp();
    bar_sync(8, 256);
    if (lane == 0 && f.boxes) ffn_load(f);
    __syncwarp();
    mbar_wait_idle(sb + BAR_WH, 0);
    if (lane == 1 && f.boxes) ffn_load(f);
    __syncwarp();
    bar_sync(3, 640);
    if (lane == 2) ffn_load(f);
    __syncwarp();
    bar_sync(2, 640);
#pragma unroll 1
    for (int k = 2; k < 20; k++) {
      if (lane == k && f.boxes && k > 2) ffn_load(f);
      __syncwarp();
      if (pw == 3 && k == 5 && lane == 0) {
        wait_flag(&g_iniflag[i * 32], 4 * epoch);
        mbar_arrive(sb + BAR_EP);
      }
      if (pw == 3 && k == 2) {
        if (elect()) {
          asm volatile("cp.async.bulk.tensor.2d.global.shared::cta.tile.bulk_group [%0, {%2,%3}], [%1];"
                       ::"l"(&tm_ini), "r"(sb + OFF_B), "r"(j * 112), "r"(i * 64) : "memory");
          asm volatile("cp.async.bulk.commit_group;\ncp.async.bulk.wait_group 0;" ::: "memory");
          mbar_arrive(sb + BAR_OI);
          fence_async_global();
          publish(&g_iniflag[i * 32]);
        }
        __syncwarp();
      }
    }
    mbar_wait_idle(sb + BAR_END, 0);
    if (blockIdx.x == 0 && tid == 512) g_s.epoch[0] = epoch;
  } else {
    TSG(90);
    uint2 w[4];
    const uint32_t xbar = sb + BAR_X + (tid >> 7) * 8;
    if ((tid & 127) == 0) {
      mbar_init(xbar, 1);
      asm volatile("fence.mbarrier_init.release.cluster;" ::: "memory");
      mbar_expect(xbar, 14336);
      bulk_load(sb + OFF_A + (tid >> 7) * 14336, p.x + (size_t)(i * 64 + (tid >> 7) * 16) * DM, 14336, xbar);
    }
    __syncwarp();
    TSD(30, tid);
    const __nv_bfloat16* wkv = (j < 2 ? p.wk : p.wv) + (j & 1) * 16 + (tid >> 2) * 28 + (tid & 3) * 4;
#pragma unroll
    for (int m = 0; m < 4; m++) {
      w[m] = make_uint2(0u, 0u);
      asm volatile("{.reg .pred p; setp.ne.u32 p, %3, 0; @p ld.global.nc.v2.u32 {%0,%1}, [%2];}"
                   : "+r"(w[m].x), "+r"(w[m].y)
                   : "l"(wkv + m * 128 * 28), "r"((uint32_t)((m < 3 || tid < 256) && !((j & 1) && (tid & 3) == 3))));
    }
    const int warp = __shfl_sync(0xffffffffu, tid >> 5, 0);
    const int wg = warp >> 2;
    const bool lead = (tid & 127) == 0;
    {
      const int wl = warp & 3, q4 = lane & 3, row = tid >> 3, c8 = tid & 7, r0 = wl * 16 + (lane >> 2);
      bar_sync(4 + wg, 128);
      const uint32_t wd0 = sb + OFF_B + (tid >> 5) * 256 + ((tid >> 1) & 1) * 128 + ((tid >> 2) & 7) * 16 + (tid & 1) * 8;
#pragma unroll
      for (int m = 0; m < 4; m++)
        if (m < 3 || tid < 256) asm volatile("st.shared.v2.u32 [%0], {%1,%2};" ::"r"(wd0 + m * 4096), "r"(w[m].x), "r"(w[m].y) : "memory");
      TS(14);
      uint4 v[7];
      mbar_wait(xbar, 0);
      TS(15);
#pragma unroll
      for (int t = 0; t < 7; t++) v[t] = lds128(sb + OFF_A + row * 896 + (c8 + 8 * t) * 16);
      bar_sync(4 + wg, 128);
      center_rows<7, true>(v, sb, row, c8, true, [&](int t) { return (row >> 3) * 7168 + t * 1024 + ((c8 ^ (row & 7)) << 4); });
      TS(27);
      bar_sync(0, 640);
      TS(1);
      if (wg == KVWG) {
        float kv[8];
        pin<8>(kv);
        uint64_t da = mkdesc(sb + OFF_A, 16, 7168, 1), db = mkdesc(sb + OFF_B, 256, 128, 0);
#pragma unroll 1
        for (int t = 0; t < 7; t++, da += 64, db += 128) {
          wg_fence();
#pragma unroll
          for (int s = 0; s < 4; s++) mma_ss_n16<1>(kv, da + s * 2, db + s * 32, t + s > 0);
          wg_commit();
        }
        TS(16);
        char* dst = reinterpret_cast<char*>(g_s.kv) + (i >> 1) * 16384 + (j >> 1) * 8192 + ((i & 1) * 64 + r0) * 64 +
                    ((((j & 1) * 2 + (q4 >> 1)) ^ ((r0 >> 1) & 3)) << 4) + (q4 & 1) * 8;
        const bool pad = (j & 1) && q4 == 2;
        const uint32_t pad0 = j == 3 ? 0x3F80u : (((POLY_MASK >> ((i & 1) * 8 + 2 * wl)) & 1) ? 0x433Fu : 0u);
        const uint32_t pad1 = j == 3 ? 0x3F80u : (((POLY_MASK >> ((i & 1) * 8 + 2 * wl + 1)) & 1) ? 0x433Fu : 0u);
        const float s0 = lds_f32(sb + OFF_RSTD + r0 * 4), s1 = lds_f32(sb + OFF_RSTD + (r0 + 8) * 4);
        wg_wait<0>();
        pin<8>(kv);
        TS(17);
        uint32_t wd[4] = {packbf(kv[0] * s0, kv[1] * s0), packbf(kv[2] * s1, kv[3] * s1), packbf(kv[4] * s0, kv[5] * s0), packbf(kv[6] * s1, kv[7] * s1)};
#pragma unroll
        for (int h = 0; h < 2; h++) {
          const uint32_t g0 = wd[h], g1 = pad ? (h ? pad1 : pad0) : wd[2 + h];
          const int src = (lane & 28) | ((q4 & 1) << 1);
          const uint32_t a0 = __shfl_sync(0xffffffffu, g0, src), a1 = __shfl_sync(0xffffffffu, g0, src + 1);
          const uint32_t b0 = __shfl_sync(0xffffffffu, g1, src), b1 = __shfl_sync(0xffffffffu, g1, src + 1);
          *reinterpret_cast<uint2*>(dst + h * 512) = make_uint2(q4 < 2 ? a0 : b0, q4 < 2 ? a1 : b1);
        }
        bar_arrive(11, POLL_LATE ? 192 : 160);
        bar_arrive(3, 384);
        TS(18);
        const float nk = max_row_norm2<2>(wd, lds32(sb + OFF_RSTD) >> 31);
        if (lane == 0 && j < 2) g_kmax[(i * 4 + wl) * 2 + j] = (unsigned short)((__float_as_uint(nk) + 0xFFFFu) >> 16);
        bar_arrive(2, 160);
      }
      if ((wg & 1) != KVWG) {
        bar_sync(3, 384);
        float qa[32];
        uint64_t db = mkdesc(sb + OFF_C + (wg >> 1) * 57344, 16, 1024, 1);
#pragma unroll
        for (int h = 0; h < 4; h++) {
          mbar_wait(sb + BAR_WQ + h * 8, 0);
          if (h == 0) TS(19);
          if (h == 3) TS(20);
          if (!QNOWAIT || h == 0) pin<32>(qa);
          wg_fence();
#pragma unroll
          for (int s = 7 * h; s < 7 * h + 7; s++) mma_ss_n64<1>(qa, mkdesc(sb + OFF_A + (s >> 2) * 1024 + (s & 3) * 32, 16, 7168, 1), db + s * 128, s > 0);
          wg_commit();
          if (!QNOWAIT) wg_wait<0>();
        }
        constexpr float QSCALE = 1.4426950408889634f * 0.1889822365046136f;
        const float s0 = lds_f32(sb + OFF_RSTD + r0 * 4) * QSCALE, s1 = lds_f32(sb + OFF_RSTD + (r0 + 8) * 4) * QSCALE;
        wg_wait<0>();
        pin<32>(qa);
        const uint32_t qt = sb + OFF_Q + (wg & 2) * 4096 + r0 * 64, sw = (r0 >> 1) & 3;
        uint32_t a8[8], b8[8];
#pragma unroll
        for (int g = 0; g < 7; g++) {
          const uint32_t w0 = packbf(qa[4 * g] * s0, qa[4 * g + 1] * s0), w1 = packbf(qa[4 * g + 2] * s1, qa[4 * g + 3] * s1);
          const bool mine = g < 3 || (g == 3 && q4 < 2);
          if (g < 4) { a8[2 * g] = mine ? w0 : 0u; a8[2 * g + 1] = mine ? w1 : 0u; }
          if (g >= 3) { b8[2 * g - 6] = mine ? 0u : w0; b8[2 * g - 5] = mine ? 0u : w1; }
          const uint32_t dst = mine ? qt + ((g ^ sw) << 4) + q4 * 4 : qt + 4096 + (((g - (q4 < 2 ? 4 : 3)) ^ sw) << 4) + (q4 ^ 2) * 4;
          sts32(dst, w0);
          sts32(dst + 512, w1);
        }
        const uint32_t pad = qt + (q4 >> 1) * 4096 + ((3 ^ sw) << 4) + 8 + (q4 & 1) * 4;
        sts32(pad, (q4 & 1) ? 0u : 0x3F80u);
        sts32(pad + 512, (q4 & 1) ? 0u : 0x3F80u);
        fence_async_smem();
        bar_arrive(9 + (wg >> 1), 256);
        if (lead)
          for (int s = 0; s < 2; s++) { mbar_arrive(sb + BAR_KVE + s * 8); mbar_arrive(sb + BAR_KVE + s * 8); }
        const uint32_t zero = lds32(pad) >> 16;
        const float nq = fmaxf(max_row_norm2<4>(a8, zero), max_row_norm2<4>(b8, zero));
        if (lane == 0) sts32(sb + OFF_QMAX + ((wg >> 1) * 4 + wl) * 4, __float_as_uint(nq));
        bar_sync(4 + wg, 128);
      } else {
        bar_sync(9 + (wg >> 1), 256);
      }
      TS(3);
    }

    asm volatile("setmaxnreg.inc.sync.aligned.u32 112;");
    float O[16];
    {
      const uint64_t dq = mkdesc(sb + OFF_Q + wg * 4096, 16, 512, 2);
      float S[32];
      uint32_t Pa[16], Pb[16];
#pragma unroll
      for (int k = 0; k < 16; k++) { O[k] = 0.f; Pb[k] = 0u; }
#pragma unroll
      for (int k = 0; k < 32; k++) S[k] = 0.f;
      pin<16>(O);
      pin<32>(S);
      pin<16>(Pb);
      const uint64_t d0 = mkdesc(sb, 16, 512, 2);
      uint64_t dc = d0 + 4096, dp = dc;
      uint32_t arr = 0, bar = sb + BAR_KVF + 16, phase = 0;
      mbar_wait(sb + BAR_KVF + 24, 0);
      TS(4);
      TSG(91);
#pragma unroll 1
      for (int n = 0; n < 8; n++) {
        attn_step<POLY_MASK & 255>(S, O, Pb, Pa, dq, dc, dp + 768, 0, 0, 0, false, false);
        attn_step<(POLY_MASK >> 8)>(S, O, Pa, Pb, dq, dc + 256, dc + 512, arr, 0, 0, true, false);
        if (n == 0) mbar_wait(bar, 0);
        attn_step<POLY_MASK & 255>(S, O, Pb, Pa, dq, dc + 1024, dc + 768, 0, 0, 0, false, false);
        arr = (lead && n < 5) ? bar + (BAR_KVE - BAR_KVF) : 0u;
        const bool wrap = n == 0 || n == 3 || n == 6;
        phase ^= (n == 2 || n == 5);
        bar = n == 7 ? bar : wrap ? bar - 16 : bar + 8;
        attn_step<(POLY_MASK >> 8)>(S, O, Pa, Pb, dq, dc + 1280, dc + 1536, 0, bar, phase, false, true);
        dp = dc + 1024;
        dc = wrap ? d0 : dc + 2048;
        TSA(32 + n);
      }
      int slot = 2;
      wg_fence();
      pv_mma(O, Pb, dp + 768);
      wg_commit();
      const uint32_t slow = lds32(sb + OFF_SLOW);
      wg_wait<0>();
      pin<16>(O);
      if (__any_sync(0xffffffffu, slow)) {
        if (lead)
          for (int s = 0; s < 3; s++) mbar_arrive(sb + BAR_KVE + s * 8);
        const int r = tid & 63;
        sts32(sb + OFF_Q + wg * 4096 + r * 64 + ((3 ^ ((r >> 1) & 3)) << 4) + 8, 0u);
        fence_async_smem();
        bar_sync(4 + wg, 128);
        float m0 = -__int_as_float(0x7f800000), m1 = m0;
#pragma unroll
        for (int k = 0; k < 16; k++) O[k] = 0.f;
#pragma unroll 1
        for (int b = 0; b < 32; b++) {
          if ((b & 3) == 0) mbar_wait(sb + BAR_KVF + (slot >> 1) * 8, phase);
          dc = mkdesc(sb + slot * 16384 + (b & 1) * 4096, 16, 512, 2);
          pin<32>(S);
          wg_fence();
          qk_mma(S, dq, dc);
          wg_commit();
          wg_wait<0>();
          pin<32>(S);
          float x0 = m0, x1 = m1;
#pragma unroll
          for (int g = 0; g < 8; g++) {
            x0 = fmaxf(x0, fmaxf(S[4 * g], S[4 * g + 1]));
            x1 = fmaxf(x1, fmaxf(S[4 * g + 2], S[4 * g + 3]));
          }
          x0 = fmaxf(x0, __shfl_xor_sync(0xffffffffu, x0, 1)); x1 = fmaxf(x1, __shfl_xor_sync(0xffffffffu, x1, 1));
          x0 = fmaxf(x0, __shfl_xor_sync(0xffffffffu, x0, 2)); x1 = fmaxf(x1, __shfl_xor_sync(0xffffffffu, x1, 2));
          const float a0 = ex2(m0 - x0), a1 = ex2(m1 - x1);
          m0 = x0;
          m1 = x1;
#pragma unroll
          for (int g = 0; g < 4; g++) { O[4 * g] *= a0; O[4 * g + 1] *= a0; O[4 * g + 2] *= a1; O[4 * g + 3] *= a1; }
#pragma unroll
          for (int g = 0; g < 8; g++) {
            Pa[2 * g] = packbf(ex2(S[4 * g] - m0), ex2(S[4 * g + 1] - m0));
            Pa[2 * g + 1] = packbf(ex2(S[4 * g + 2] - m1), ex2(S[4 * g + 3] - m1));
          }
          pin<16>(Pa);
          pin<16>(O);
          wg_fence();
          pv_mma(O, Pa, dc + 512);
          wg_commit();
          wg_wait<0>();
          pin<16>(O);
          if (b & 1) {
            if (lead && (b & 2)) mbar_arrive(sb + BAR_KVE + (slot >> 1) * 8);
            slot = slot == 5 ? 0 : slot + 1;
            phase ^= (slot == 4);
          }
        }
      }
    }
    TS(5);
    TSG(92);
    post_attention(O, warp, p, &tm_out);
    TSG(93);
    __syncwarp();
    if (lane == 0) mbar_arrive(sb + BAR_END);
  }
}

typedef CUresult (*EncodeTiledFn)(CUtensorMap*, CUtensorMapDataType, cuuint32_t, void*, const cuuint64_t*, const cuuint64_t*,
                                  const cuuint32_t*, const cuuint32_t*, CUtensorMapInterleave, CUtensorMapSwizzle,
                                  CUtensorMapL2promotion, CUtensorMapFloatOOBfill);

static CUtensorMap make_map(EncodeTiledFn enc, const void* base, int rank, const cuuint64_t* dims, const cuuint64_t* strides,
                            const cuuint32_t* box, CUtensorMapSwizzle swz) {
  CUtensorMap m;
  const cuuint32_t es[4] = {1, 1, 1, 1};
  enc(&m, CU_TENSOR_MAP_DATA_TYPE_BFLOAT16, rank, const_cast<void*>(base), dims, strides, box, es, CU_TENSOR_MAP_INTERLEAVE_NONE, swz,
      CU_TENSOR_MAP_L2_PROMOTION_L2_128B, CU_TENSOR_MAP_FLOAT_OOB_FILL_NONE);
  return m;
}

extern "C" void kernel_launch(void* const* d_in, const int* in_sizes, int n_in, void* d_out, int out_size) {
  static EncodeTiledFn enc = nullptr;
  if (!enc) {
    void* fn = nullptr;
    cudaDriverEntryPointQueryResult st;
    cudaGetDriverEntryPoint("cuTensorMapEncodeTiled", &fn, cudaEnableDefault, &st);
    enc = reinterpret_cast<EncodeTiledFn>(fn);
    cudaFuncSetAttribute(fused_block_kernel, cudaFuncAttributeMaxDynamicSharedMemorySize, SMEM_BYTES);
  }
  Params p;
  p.x = static_cast<const __nv_bfloat16*>(d_in[0]);
  p.wq = static_cast<const __nv_bfloat16*>(d_in[1]);
  p.wk = static_cast<const __nv_bfloat16*>(d_in[2]);
  p.wv = static_cast<const __nv_bfloat16*>(d_in[3]);
  p.wo = static_cast<const __nv_bfloat16*>(d_in[4]);
  p.w1 = static_cast<const __nv_bfloat16*>(d_in[6]);
  p.b1 = static_cast<const __nv_bfloat16*>(d_in[7]);
  p.w2 = static_cast<const __nv_bfloat16*>(d_in[8]);
  p.b2 = static_cast<const __nv_bfloat16*>(d_in[9]);
  p.out = static_cast<__nv_bfloat16*>(d_out);
  const cuuint64_t d_sq[2] = {DM, DM}, s_d[1] = {DM * 2};
  const cuuint32_t b_wq[2] = {64, 112}, b_64[2] = {64, 64};
  const cuuint64_t d_wo[4] = {16, 28, DM / 16, 16}, s_wo[3] = {DM * 2, 32, 28 * DM * 2};
  const cuuint32_t b_wo[4] = {16, 32, 7, 2};
  const cuuint64_t d_w1[2] = {FF, DM}, s_w1[1] = {FF * 2}, d_w2[2] = {DM, FF}, d_o[2] = {DM, SEQ};
  const CUtensorMap tm_wq = make_map(enc, d_in[1], 2, d_sq, s_d, b_wq, CU_TENSOR_MAP_SWIZZLE_128B);
  const CUtensorMap tm_wo = make_map(enc, d_in[4], 4, d_wo, s_wo, b_wo, CU_TENSOR_MAP_SWIZZLE_32B);
  const CUtensorMap tm_w1 = make_map(enc, d_in[6], 2, d_w1, s_w1, b_64, CU_TENSOR_MAP_SWIZZLE_128B);
  const CUtensorMap tm_w2 = make_map(enc, d_in[8], 2, d_w2, s_d, b_64, CU_TENSOR_MAP_SWIZZLE_128B);
  const CUtensorMap tm_out = make_map(enc, d_out, 2, d_o, s_d, b_64, CU_TENSOR_MAP_SWIZZLE_128B);
  const cuuint32_t b_ini[2] = {112, 64};
  const CUtensorMap tm_ini = make_map(enc, d_out, 2, d_o, s_d, b_ini, CU_TENSOR_MAP_SWIZZLE_NONE);
  fused_block_kernel<<<NCTA, NTHREADS, SMEM_BYTES>>>(p, tm_wq, tm_wo, tm_w1, tm_w2, tm_out, tm_ini);
}
```
